```python
import torch

def _softmax(x, axis=-1):
    return torch.softmax(x, dim=axis)
def _gelu(x):
    return torch.nn.functional.gelu(x, approximate="tanh")
def _silu(x):
    return torch.nn.functional.silu(x)
def _sigmoid(x):
    return torch.sigmoid(x)
def _layernorm(x, axis=-1, eps=1e-5):
    m = x.mean(dim=axis, keepdim=True)
    v = x.var(dim=axis, keepdim=True, unbiased=False)
    return (x - m) / torch.sqrt(v + eps)
def _scatter_add(tgt, idx, src, axis=0):
    return tgt.clone().index_add_(axis, idx, src)
def _segment_sum(src, seg, n):
    out = torch.zeros((n,) + src.shape[1:], dtype=src.dtype)
    return out.index_add_(0, seg, src)
def _pad(x, pw):
    flat = tuple(v for pair in reversed(pw) for v in pair)
    return torch.nn.functional.pad(x, flat)

kernel_name = 'recurrent_scan__gqa_block_cached__glu_gated_glu__decode'

def setup_inputs():

    _w = (lambda a: (lambda t: t.to(torch.bfloat16) if t.is_floating_point() else t)(torch.as_tensor(a)))
    def _A_setup():
        B, Sq, D = 8, 1, 512
        Hq, Hkv, Sk, Dh = 32, 8, 4096, 128
        assert Hq % Hkv == 0, (Hq, Hkv)
        return {
            "x": _w((lambda *s: torch.randn(*s, dtype=torch.bfloat16) * 0.05)(B, Sq, D)),
            "k_cache": _w((lambda *s: torch.randn(*s, dtype=torch.bfloat16) * 1.6)(B, Hkv, Sk, Dh)),
            "v_cache": _w((lambda *s: torch.randn(*s, dtype=torch.bfloat16) * 0.2)(B, Hkv, Sk, Dh)),
            "wq": _w((lambda *s: torch.randn(*s, dtype=torch.bfloat16) * 1.6)(D, Hq * Dh) * (D ** -0.5)),
            "wo": _w((lambda *s: torch.randn(*s, dtype=torch.bfloat16) * 0.2)(Hq * Dh, D) * ((Hq * Dh) ** -0.5)),
        }
    _A_in = _A_setup()

    def _B_setup():
        B, S, D, F = 8, 1, 512, 1792
        return {
            "x": _w((lambda *s: torch.randn(*s, dtype=torch.bfloat16) * 0.05)(B, S, D)),
            "w_gate": _w((lambda *s: torch.randn(*s, dtype=torch.bfloat16) * 1.6)(D, F)),
            "w_up": _w((lambda *s: torch.randn(*s, dtype=torch.bfloat16) * 0.1)(D, F)),
            "w_down": _w((lambda *s: torch.randn(*s, dtype=torch.bfloat16) * 0.1)(F, D)),
        }
    _B_in = _B_setup()

    return {
        "A_x": _A_in["x"],
        "A_k_cache": _A_in["k_cache"],
        "A_v_cache": _A_in["v_cache"],
        "A_wq": _A_in["wq"],
        "A_wo": _A_in["wo"],
        "B_x": _B_in["x"],
        "B_w_gate": _B_in["w_gate"],
        "B_w_up": _B_in["w_up"],
        "B_w_down": _B_in["w_down"],
    }

def reference(A_x, A_k_cache, A_v_cache, A_wq, A_wo, B_x, B_w_gate, B_w_up, B_w_down):
    def _A_ref(x, k_cache, v_cache, wq, wo):
        B, Sq, D = x.shape
        Hq, Dh = 32, 128
        Hkv = k_cache.shape[1]
        rep = Hq // Hkv
        q = (lambda x, *d: x.permute(*d))((x @ wq).reshape(B, Sq, Hq, Dh), 0, 2, 1, 3)
        k = (lambda x, n, axis: torch.repeat_interleave(x, n, dim=axis))(k_cache, rep, axis=1)
        v = (lambda x, n, axis: torch.repeat_interleave(x, n, dim=axis))(v_cache, rep, axis=1)
        scores = torch.einsum("bhqd,bhkd->bhqk", q, k) * (Dh ** -0.5)
        p = _softmax(scores, axis=-1)
        o = torch.einsum("bhqk,bhkd->bhqd", p, v)
        return (lambda x, *d: x.permute(*d))(o, 0, 2, 1, 3).reshape(B, Sq, Hq * Dh) @ wo

    def _B_ref(x, w_gate, w_up, w_down):
        g = torch.einsum("bsd,df->bsf", x, w_gate)
        u = torch.einsum("bsd,df->bsf", x, w_up)
        h = _sigmoid(g) * u
        return torch.einsum("bsf,fd->bsd", h, w_down)

    x = A_x
    xn = _layernorm(x, axis=-1)
    s = _A_ref(xn, A_k_cache, A_v_cache, A_wq, A_wo)
    g = _silu(_B_ref(xn, B_w_gate, B_w_up, B_w_down))
    return x + s * g
```

```cpp
#include <cuda_runtime.h>
#include <cuda_bf16.h>
#include <cuda.h>
#include <stdint.h>

namespace {

constexpr int kB = 8, kD = 512, kHkv = 8, kSk = 4096, kDh = 128, kF = 1792;
constexpr int kAttnCtas = 128, kGluCtas = 4, kGrid = kAttnCtas + kGluCtas;
constexpr int kConsumerWarps = 8;
constexpr int kThreads = (kConsumerWarps + 2) * 32;

constexpr int kSlotBytes = 16384;
constexpr int kSlots = 12;
constexpr int kFirstLoads = 4;
constexpr int kWindow = 4;
constexpr int kGluWindow = 8;
constexpr int kQReadAfter = 7;
constexpr int kPaceFrom = 3, kPaceTiles = 30;
constexpr int kLeadStep1 = -48, kLeadStep2 = 32;
constexpr int kPaceStep2Until = 26;
constexpr int kClearAt = 16;
constexpr int kReportAt = 63;
constexpr int kWoAfter = 64;
constexpr int kTileKeys = 64;
constexpr int kKeysPerCta = kSk / 2;
constexpr int kTiles = kKeysPerCta / kTileKeys;
constexpr int kAttnLoads = 2 + 2 * kTiles + 2;
static_assert(kAttnLoads - 5 == 63, "swap of loads 63 and 64");
constexpr int kGluCols = kF / kGluCtas;
constexpr int kGluChunks = kGluCols / 64;
constexpr int kGluSteps1 = kD / 16;
constexpr int kGluSteps2 = kGluCols / 16;
constexpr int kGluLoads = 2 * kGluSteps1 + kGluSteps2;
constexpr int kSpinLimit = 1 << 21;
constexpr int kGateCopies = 16;

constexpr int kXnPitch = kD + 8;
constexpr int kActPitch = kDh + 8;
constexpr int kHPitch = kGluCols + 8;
constexpr int kActFragPitch = 256 + 32;

constexpr int kOffRing = 0;
constexpr int kOffXn = kSlots * kSlotBytes;
constexpr int kOffAct = kOffXn + kB * kXnPitch * 2;
constexpr int kOffQ = kOffAct + kB * kActFragPitch;
constexpr int kOffO = kOffQ + 4 * kActPitch * 2;
constexpr int kOffStat = kOffO + kConsumerWarps * 4 * kDh * 4;
constexpr int kOffRed = kOffStat + kConsumerWarps * 8 * 4;
constexpr int kOffBar = kOffRed + (kConsumerWarps + 2) * 32 * 4;
constexpr int kOffTag = kOffBar + (2 * kSlots + 2) * 8;
constexpr int kSmemBytes = kOffTag + 16;
static_assert(kB * kHPitch * 2 <= kConsumerWarps * 4 * kDh * 4, "h buffer aliases the O buffer");
static_assert(kSmemBytes <= 232448, "shared memory budget");

static_assert(kSlots % 2 == 0, "K/V and weight tile pairs occupy adjacent slots");
constexpr uint32_t kTagMask = 15u;

struct Maps {
    CUtensorMap k, v, wq, wo, wg, wu, wd;
};

__device__ uint32_t g_epoch[kGrid];
__device__ __align__(128) uint32_t g_qpart[kHkv * kB * 4 * 4 * kDh];
__device__ __align__(128) uint32_t g_opart[kHkv * 4 * kB * 2 * kDh];
__device__ __align__(128) uint32_t g_progress[32];
__device__ __align__(128) uint32_t g_spart[4 * 32 * 32 * 32];
__device__ __align__(128) uint32_t g_gate[kGateCopies * 32];
__device__ __align__(128) uint32_t g_gpart[kGluCtas * kB * kD];

__device__ __forceinline__ uint32_t smem_u32(const void* p) { return (uint32_t)__cvta_generic_to_shared(p); }

__device__ __forceinline__ void mbar_init(uint32_t bar, int count) {
    asm volatile("mbarrier.init.shared::cta.b64 [%0], %1;" ::"r"(bar), "r"(count) : "memory");
}
__device__ __forceinline__ void mbar_expect_tx(uint32_t bar, uint32_t bytes) {
    asm volatile("mbarrier.arrive.expect_tx.shared::cta.b64 _, [%0], %1;" ::"r"(bar), "r"(bytes) : "memory");
}
__device__ __forceinline__ void mbar_arrive(uint32_t bar) {
    asm volatile("mbarrier.arrive.shared::cta.b64 _, [%0];" ::"r"(bar) : "memory");
}
__device__ __forceinline__ void mbar_wait(uint32_t bar, uint32_t parity) {
    uint32_t ok;
    int spins = 0;
    do {
        asm volatile(
            "{\n .reg .pred p;\n mbarrier.try_wait.parity.shared::cta.b64 p, [%1], %2;\n selp.u32 %0, 1, 0, p;\n}"
            : "=r"(ok) : "r"(bar), "r"(parity) : "memory");
    } while (!ok && ++spins < kSpinLimit);
}
__device__ __forceinline__ void tma_load_3d_hint(uint32_t dst, const CUtensorMap* map, uint32_t bar, int row, int chunk,
                                                 uint64_t policy) {
    asm volatile(
        "cp.async.bulk.tensor.3d.shared::cluster.global.mbarrier::complete_tx::bytes.L2::cache_hint "
        "[%0], [%1, {%3, %4, %5}], [%2], %6;"
        ::"r"(dst), "l"(map), "r"(bar), "r"(0), "r"(row), "r"(chunk), "l"(policy) : "memory");
}
__device__ __forceinline__ void consumer_sync() { asm volatile("bar.sync 1, 256;" ::: "memory"); }

__device__ __forceinline__ void ldsm_x4(uint32_t addr, uint32_t (&r)[4]) {
    asm volatile("ldmatrix.sync.aligned.m8n8.x4.shared.b16 {%0,%1,%2,%3}, [%4];"
                 : "=r"(r[0]), "=r"(r[1]), "=r"(r[2]), "=r"(r[3]) : "r"(addr) : "memory");
}
__device__ __forceinline__ void ldsm_x4_t(uint32_t addr, uint32_t (&r)[4]) {
    asm volatile("ldmatrix.sync.aligned.m8n8.x4.trans.shared.b16 {%0,%1,%2,%3}, [%4];"
                 : "=r"(r[0]), "=r"(r[1]), "=r"(r[2]), "=r"(r[3]) : "r"(addr) : "memory");
}
__device__ __forceinline__ void mma_bf16(float (&c)[4], const uint32_t (&a)[4], uint32_t b0, uint32_t b1) {
    asm volatile(
        "mma.sync.aligned.m16n8k16.row.col.f32.bf16.bf16.f32 {%0,%1,%2,%3}, {%4,%5,%6,%7}, {%8,%9}, {%0,%1,%2,%3};"
        : "+f"(c[0]), "+f"(c[1]), "+f"(c[2]), "+f"(c[3])
        : "r"(a[0]), "r"(a[1]), "r"(a[2]), "r"(a[3]), "r"(b0), "r"(b1));
}
__device__ __forceinline__ uint32_t movmatrix_t(uint32_t a) {
    uint32_t d;
    asm volatile("movmatrix.sync.aligned.m8n8.trans.b16 %0, %1;" : "=r"(d) : "r"(a));
    return d;
}
__device__ __forceinline__ uint32_t pack_bf16(float lo, float hi) {
    uint32_t d;
    asm("cvt.rn.bf16x2.f32 %0, %1, %2;" : "=r"(d) : "f"(hi), "f"(lo));
    return d;
}
__device__ __forceinline__ float round_bf16(float x) { return __bfloat162float(__float2bfloat16_rn(x)); }
__device__ __forceinline__ float ex2(float x) {
    float y;
    asm("ex2.approx.ftz.f32 %0, %1;" : "=f"(y) : "f"(x));
    return y;
}
__device__ __forceinline__ uint32_t lds32(uint32_t addr) {
    uint32_t v;
    asm volatile("ld.shared.b32 %0, [%1];" : "=r"(v) : "r"(addr) : "memory");
    return v;
}

__device__ __forceinline__ uint2 lds64(uint32_t addr) {
    uint2 v;
    asm volatile("ld.shared.v2.b32 {%0, %1}, [%2];" : "=r"(v.x), "=r"(v.y) : "r"(addr) : "memory");
    return v;
}
__device__ __forceinline__ void sts64(uint32_t addr, uint32_t a, uint32_t b) {
    asm volatile("st.shared.v2.b32 [%0], {%1, %2};" ::"r"(addr), "r"(a), "r"(b) : "memory");
}

__device__ __forceinline__ uint32_t tag_word(float v, uint32_t tag) { return (__float_as_uint(v) & ~kTagMask) | tag; }
__device__ __forceinline__ float untag(uint32_t w) { return __uint_as_float(w & ~kTagMask); }
__device__ __forceinline__ void st_word(uint32_t* p, uint32_t w) {
    asm volatile("st.relaxed.gpu.global.b32 [%0], %1;" ::"l"(p), "r"(w) : "memory");
}
__device__ __forceinline__ void st_word2(uint32_t* p, uint32_t a, uint32_t b) {
    asm volatile("st.relaxed.gpu.global.v2.b32 [%0], {%1, %2};" ::"l"(p), "r"(a), "r"(b) : "memory");
}
__device__ __forceinline__ void st_word4(uint32_t* p, uint32_t a, uint32_t b, uint32_t c, uint32_t d) {
    asm volatile("st.relaxed.gpu.global.v4.b32 [%0], {%1, %2, %3, %4};" ::"l"(p), "r"(a), "r"(b), "r"(c), "r"(d) : "memory");
}
__device__ __forceinline__ uint32_t ld_word(const uint32_t* p) {
    uint32_t w;
    asm volatile("ld.relaxed.gpu.global.b32 %0, [%1];" : "=r"(w) : "l"(p) : "memory");
    return w;
}
__device__ __forceinline__ uint4 ldg_nc(const uint4* p) {
    uint4 w;
    asm volatile("ld.global.nc.v4.b32 {%0, %1, %2, %3}, [%4];" : "=r"(w.x), "=r"(w.y), "=r"(w.z), "=r"(w.w) : "l"(p));
    return w;
}
__device__ __forceinline__ uint32_t ld_acquire(const uint32_t* p) {
    uint32_t w;
    asm volatile("ld.acquire.gpu.global.b32 %0, [%1];" : "=r"(w) : "l"(p) : "memory");
    return w;
}
__device__ __forceinline__ uint2 ld_word2(const uint32_t* p) {
    uint2 w;
    asm volatile("ld.relaxed.gpu.global.v2.b32 {%0, %1}, [%2];" : "=r"(w.x), "=r"(w.y) : "l"(p) : "memory");
    return w;
}
__device__ __forceinline__ uint4 ld_word4(const uint32_t* p) {
    uint4 w;
    asm volatile("ld.relaxed.gpu.global.v4.b32 {%0, %1, %2, %3}, [%4];"
                 : "=r"(w.x), "=r"(w.y), "=r"(w.z), "=r"(w.w) : "l"(p) : "memory");
    return w;
}
__device__ __forceinline__ uint32_t tag_diff(uint2 w, uint32_t tag) { return ((w.x ^ tag) | (w.y ^ tag)) & kTagMask; }

__device__ __forceinline__ uint32_t mail_word(float v) { return (__float_as_uint(v) & ~kTagMask) | 1u; }
__device__ __forceinline__ uint32_t and3(uint32_t a, uint32_t b, uint32_t c) {
    uint32_t d;
    asm("lop3.b32 %0, %1, %2, %3, 0x80;" : "=r"(d) : "r"(a), "r"(b), "r"(c));
    return d;
}
__device__ __forceinline__ uint32_t mail_full(uint4 w) { return and3(and3(w.x, w.y, w.z), w.w, 1u); }
__device__ __forceinline__ uint32_t mail_full(uint4 u, uint4 v) {
    return and3(and3(u.x, u.y, u.z), and3(u.w, v.x, v.y), and3(v.z, v.w, 1u));
}

template <class T>
__device__ __forceinline__ T* pin(T* p) {
    asm volatile("mov.b64 %0, %0;" : "+l"(p));
    return p;
}
__device__ __forceinline__ uint32_t pin(uint32_t v) {
    asm volatile("mov.b32 %0, %0;" : "+r"(v));
    return v;
}

__device__ __forceinline__ float rcp_fast(float x) {
    float y;
    asm("rcp.approx.ftz.f32 %0, %1;" : "=f"(y) : "f"(x));
    return y;
}
__device__ __forceinline__ float sigmoid_fast(float x) { return rcp_fast(1.0f + ex2(-1.4426950408889634f * x)); }

__device__ __forceinline__ void layernorm_row(const uint4 (&raw)[2], int row, int lane, unsigned char* xn_smem) {
    float v[16];
#pragma unroll
    for (int i = 0; i < 2; i++) {
        const uint32_t w[4] = {raw[i].x, raw[i].y, raw[i].z, raw[i].w};
#pragma unroll
        for (int j = 0; j < 4; j++) {
            v[i * 8 + 2 * j] = __uint_as_float(w[j] << 16);
            v[i * 8 + 2 * j + 1] = __uint_as_float(w[j] & 0xffff0000u);
        }
    }
    float s = 0.f;
#pragma unroll
    for (int i = 0; i < 16; i++) s += v[i];
#pragma unroll
    for (int o = 16; o > 0; o >>= 1) s += __shfl_xor_sync(0xffffffffu, s, o);
    const float mean = s * (1.0f / kD);
    float q = 0.f;
#pragma unroll
    for (int i = 0; i < 16; i++) q += (v[i] - mean) * (v[i] - mean);
#pragma unroll
    for (int o = 16; o > 0; o >>= 1) q += __shfl_xor_sync(0xffffffffu, q, o);
    const float mean_b = round_bf16(mean);
    const float var_b = round_bf16(q * (1.0f / kD));
    const float inv_sd = __frcp_rn(round_bf16(__fsqrt_rn(round_bf16(var_b + 1e-5f))));
#pragma unroll
    for (int i = 0; i < 2; i++) {
        uint32_t w[4];
#pragma unroll
        for (int j = 0; j < 4; j++) {
            const uint32_t d = pack_bf16(v[i * 8 + 2 * j] - mean_b, v[i * 8 + 2 * j + 1] - mean_b);
            w[j] = pack_bf16(__uint_as_float(d << 16) * inv_sd, __uint_as_float(d & 0xffff0000u) * inv_sd);
        }
        *reinterpret_cast<uint4*>(xn_smem + (row * kXnPitch + i * 256 + lane * 8) * 2) = make_uint4(w[0], w[1], w[2], w[3]);
    }
}

__device__ __forceinline__ uint32_t proj_addr(uint32_t slot_lo, int warp, int lane) {
    const int krow = (lane & 7) + 8 * (lane >> 4);
    const int chunk = 2 * (warp & 3) + ((lane >> 3) & 1);
    return slot_lo + (warp >> 2) * 8192 + krow * 128 + ((chunk ^ (lane & 7)) << 4);
}

template <class BFrag>
__device__ __forceinline__ void proj_tile(float (&c)[4], uint32_t slot_lo, int warp, int lane, BFrag bfrag) {
    const uint32_t a_addr = proj_addr(slot_lo, warp, lane);
    float c2[4] = {0.f, 0.f, 0.f, 0.f};
    c[0] = c[1] = c[2] = c[3] = 0.f;
#pragma unroll
    for (int ks = 0; ks < 4; ks++) {
        uint32_t a[4], a2[4];
        ldsm_x4_t(a_addr + ks * 2048, a);
        ldsm_x4_t(a_addr + kSlotBytes + ks * 2048, a2);
        const uint2 b = bfrag(ks), b2 = bfrag(ks + 4);
        mma_bf16(c, a, b.x, b.y);
        mma_bf16(c2, a2, b2.x, b2.y);
    }
#pragma unroll
    for (int i = 0; i < 4; i++) c[i] += c2[i];
}

__device__ __forceinline__ void issue_load(uint32_t smem_base, int slot, const CUtensorMap* map, int row, int chunk,
                                           uint32_t bytes, uint64_t policy) {
    const uint32_t bar = smem_base + kOffBar + slot * 8;
    mbar_expect_tx(bar, bytes);
    tma_load_3d_hint(smem_base + kOffRing + slot * kSlotBytes, map, bar, row, chunk, policy);
}

__global__ void __launch_bounds__(kThreads, 1)
fused_decode_kernel(const __nv_bfloat16* __restrict__ x, __nv_bfloat16* __restrict__ out, const char* __restrict__ wq,
                    const __grid_constant__ Maps maps) {
    extern __shared__ __align__(1024) unsigned char smem[];
    const uint32_t smem_base = smem_u32(smem);
    const uint32_t ring = smem_base + kOffRing;
    const uint32_t full_bar = smem_base + kOffBar;
    const uint32_t empty_bar = full_bar + kSlots * 8;
    const uint32_t gate_bar = empty_bar + kSlots * 8;

    const int tid = threadIdx.x, warp = tid >> 5, lane = tid & 31;
    const int cta = blockIdx.x;
    const bool is_attn = cta < kAttnCtas;
    const int g = lane >> 2, t = lane & 3;
    const int hkv = cta >> 4, b = (cta >> 1) & 7, split = cta & 1;
    const int h = (cta >> 2) & 3, head = cta >> 2, quarter = cta & 3;

    if (tid == kConsumerWarps * 32) {
        asm volatile("prefetch.tensormap [%0];" ::"l"(is_attn ? &maps.wq : &maps.wg) : "memory");
        asm volatile("prefetch.tensormap [%0];" ::"l"(is_attn ? &maps.k : &maps.wu) : "memory");
        asm volatile("prefetch.tensormap [%0];" ::"l"(&maps.v) : "memory");
    }
    uint4 xraw[2];
    if (warp < kConsumerWarps) {
        if (is_attn)
            asm volatile("prefetch.global.L2 [%0];" ::"l"(wq + (size_t)(quarter * 128 + (tid >> 1)) * 8192 + head * 256 + (tid & 1) * 128));
        const uint4* src = reinterpret_cast<const uint4*>(x + warp * kD);
        xraw[0] = ldg_nc(src + lane);
        xraw[1] = ldg_nc(src + 32 + lane);
    }
    const int out_idx = (2 * h + (lane & 1)) * kD + quarter * 128 + hkv * 16 + g + 8 * ((lane >> 1) & 1);
    float* red = reinterpret_cast<float*>(smem + kOffRed);

    const int key0 = (b * kHkv + hkv) * kSk + split * kKeysPerCta;

    uint64_t kv_policy, w_policy;
    asm volatile("createpolicy.fractional.L2::evict_first.b64 %0, 1.0;" : "=l"(kv_policy));
    asm volatile("createpolicy.fractional.L2::evict_normal.b64 %0, 1.0;" : "=l"(w_policy));
    if (tid == kConsumerWarps * 32) {
        const CUtensorMap* m0 = is_attn ? &maps.wq : &maps.wg;
        const CUtensorMap* m1 = is_attn ? &maps.wq : &maps.wu;
        const int row = is_attn ? quarter * 128 : 0, chunk = is_attn ? head * 2 : quarter * kGluChunks;
        const uint32_t bytes = is_attn ? kSlotBytes : kGluChunks * 2048;
        mbar_init(full_bar, 1);
        mbar_init(full_bar + 8, 1);
        issue_load(smem_base, 0, m0, row, chunk, bytes, w_policy);
        issue_load(smem_base, 1, m1, is_attn ? row + 64 : 0, chunk, bytes, w_policy);
        mbar_init(full_bar + 16, 1);
        mbar_init(full_bar + 24, 1);
        issue_load(smem_base, 2, is_attn ? &maps.k : m0, is_attn ? key0 : 16, is_attn ? 0 : chunk, bytes, is_attn ? kv_policy : w_policy);
        issue_load(smem_base, 3, is_attn ? &maps.v : m1, is_attn ? key0 : 16, is_attn ? 0 : chunk, bytes, is_attn ? kv_policy : w_policy);
    }
    uint32_t epoch = 0;
    if (warp < kConsumerWarps) {
        if (tid == 0) epoch = g_epoch[cta] + 1;
        if (lane == 0) {
#pragma unroll 1
            for (int i = kFirstLoads + warp; i < 2 * kSlots + 2; i += kConsumerWarps) {
                const bool single = i < kSlots || i == 2 * kSlots;
                mbar_init(full_bar + i * 8, single ? 1 : (is_attn && i < 2 * kSlots ? 4 + (~i & 1) : kConsumerWarps));
            }
            asm volatile("fence.mbarrier_init.release.cluster;" ::: "memory");
        }
    } else if (tid == (kConsumerWarps + 1) * 32) {
        epoch = g_epoch[cta] + 1;
        *reinterpret_cast<uint2*>(smem + kOffTag + 8) = make_uint2(kWindow, epoch);
    }
    __syncthreads();

    if (warp == kConsumerWarps) {
        if (lane == 0) {
            const int n_loads = is_attn ? kAttnLoads : kGluLoads;
            asm volatile("prefetch.tensormap [%0];" ::"l"(is_attn ? &maps.wo : &maps.wd) : "memory");
            const volatile int* window = reinterpret_cast<const volatile int*>(smem + kOffTag + 8);
            int slot = kFirstLoads, empty_par = 1, landed = 0, land_slot = 0, land_par = 0;
#pragma unroll 1
            for (int i = kFirstLoads; i < n_loads; i++) {
                mbar_wait(empty_bar + slot * 8, empty_par);
                const int w = is_attn ? (i >= kAttnLoads - 2 ? kSlots : window[0]) : kGluWindow;
#pragma unroll 1
                for (; landed <= i - w; landed++) {
                    mbar_wait(full_bar + land_slot * 8, land_par);
                    if (++land_slot == kSlots) { land_slot = 0; land_par ^= 1; }
                }
                const CUtensorMap* map;
                int row, chunk = 0;
                uint32_t bytes = kSlotBytes;
                if (is_attn) {
                    if (i < kAttnLoads - 2) {
                        const int j = (i == kAttnLoads - 5 || i == kAttnLoads - 4) ? i ^ 127 : i;
                        map = (j & 1) ? &maps.v : &maps.k;
                        row = key0 + ((j - 2) >> 1) * kTileKeys;
                    } else {
                        if (i == kAttnLoads - 2) {
                            const uint32_t target = (window[1] - 1) * kAttnCtas + kWoAfter;
                            int spins = 0;
                            while ((int)(target - ld_word(g_gate + (cta % kGateCopies) * 32)) > 0 && ++spins < kSpinLimit) {}
                        }
                        map = &maps.wo;
                        row = head * 128 + (i & 1) * 64;
                        chunk = quarter * 2;
                    }
                } else if (i < 2 * kGluSteps1) {
                    map = (i & 1) ? &maps.wu : &maps.wg;
                    row = (i >> 1) * 16;
                    chunk = quarter * kGluChunks;
                    bytes = kGluChunks * 2048;
                } else {
                    map = &maps.wd;
                    row = quarter * kGluCols + (i - 2 * kGluSteps1) * 16;
                }
                issue_load(smem_base, slot, map, row, chunk, bytes, (is_attn && i < kAttnLoads - 2) ? kv_policy : w_policy);
                if (++slot == kSlots) { slot = 0; empty_par ^= 1; }
            }
        }
        return;
    }

    if (warp == kConsumerWarps + 1) {
        if (is_attn) {
            volatile int* window = reinterpret_cast<volatile int*>(smem + kOffTag + 8);
            uint32_t expect = (epoch - 1) * (kPaceTiles * kAttnCtas) + kAttnCtas / 2;
            if (lane == 0) {
                mbar_wait(full_bar, 0);
                mbar_arrive(empty_bar);
            }
            int slot = 2, par = 0;
#pragma unroll 1
            for (int j = 0; j < kPaceTiles; j++) {
                if (lane == 0) {
                    mbar_wait(full_bar + slot * 8, par);
                    mbar_arrive(empty_bar + slot * 8);
                    uint32_t n;
                    asm volatile("atom.relaxed.gpu.global.add.u32 %0, [%1], 1;" : "=r"(n) : "l"(g_progress) : "memory");
                    const int lead = (int)(expect - n);
                    if (j >= kPaceFrom) window[0] = kWindow - (lead > kLeadStep1) - (lead > kLeadStep2 && j < kPaceStep2Until);
                }
                __syncwarp();
                if (j == kClearAt) {
#pragma unroll
                    for (int i = 0; i < 4; i++)
                        st_word4(g_opart + ((((hkv * 4 + i) * kB + b) * 2 + split) * kDh + lane * 4), 0, 0, 0, 0);
#pragma unroll
                    for (int i = 0; i < 8; i++)
                        st_word4(g_spart + ((quarter * 32 + i * 4 + (lane >> 3)) * 32 + head) * 32 + (lane & 7) * 4, 0, 0, 0, 0);
                    __syncwarp();
                    asm volatile("fence.acq_rel.gpu;" ::: "memory");
                }
                expect += kAttnCtas;
                slot += 2;
                if (slot == kSlots) { slot = 0; par ^= 1; }
            }
            static_assert(2 + 2 * kPaceTiles + kSlots >= kAttnLoads && kReportAt >= 2 * kPaceTiles,
                          "slots after the paced range are not reused");
            static_assert(2 + 2 * (kClearAt + 1) + kSlots < kAttnLoads - 4, "a slot released after the clear is reused for K");
            if (lane == 0) mbar_wait(full_bar + (kReportAt % kSlots) * 8, (kReportAt / kSlots) & 1);
            __syncwarp();
            if (lane < kGateCopies)
                asm volatile("red.relaxed.gpu.global.add.u32 [%0], 1;" ::"l"(g_gate + lane * 32) : "memory");
            if (lane == 0) {
                const uint32_t target = epoch * kAttnCtas;
                const uint32_t* count = g_gate + (cta % kGateCopies) * 32;
                int spins = 0;
                while ((int)(target - ld_acquire(count)) > 0 && ++spins < kSpinLimit) {}
                mbar_arrive(gate_bar);
            }
            const uint32_t tag = 1 + __shfl_sync(0xffffffffu, epoch, 0) % kTagMask;
            const float xv = __bfloat162float(x[out_idx]);
            uint32_t gw[kGluCtas];
            int spins = 0;
            uint32_t bad;
            do {
                bad = 0;
#pragma unroll
                for (int k = 0; k < kGluCtas; k++) gw[k] = ld_word(g_gpart + out_idx + k * kB * kD);
#pragma unroll
                for (int k = 0; k < kGluCtas; k++) bad |= (gw[k] ^ tag) & kTagMask;
            } while (bad && ++spins < kSpinLimit);
            const float gl = round_bf16((untag(gw[0]) + untag(gw[1])) + (untag(gw[2]) + untag(gw[3])));
            red[256 + lane] = round_bf16(gl * sigmoid_fast(gl));
            red[288 + lane] = xv;
            asm volatile("bar.arrive 2, 288;" ::: "memory");
        }
        return;
    }

    if (tid == 0) {
        g_epoch[cta] = epoch;
        *reinterpret_cast<uint32_t*>(smem + kOffTag) = 1 + epoch % kTagMask;
    }
    layernorm_row(xraw, warp, lane, smem + kOffXn);
    consumer_sync();
    const uint32_t tag = *reinterpret_cast<const uint32_t*>(smem + kOffTag);

    if (is_attn) {
        {
            mbar_wait(full_bar + 0, 0);
            mbar_wait(full_bar + 8, 0);
            const uint32_t xa = smem_base + kOffXn + (g * kXnPitch + quarter * 128 + 2 * t) * 2;
            float c[4];
            proj_tile(c, ring, warp, lane, [&](int ks) { return make_uint2(lds32(xa + ks * 32), lds32(xa + ks * 32 + 16)); });
            uint32_t* dst = g_qpart + (((hkv * kB + 2 * t) * 4 + h) * 4 + quarter) * kDh + warp * 16 + g;
#pragma unroll
            for (int i = 0; i < 4; i++) st_word(dst + (i & 1) * 16 * kDh + 8 * (i >> 1), tag_word(c[i], tag));
        }
        consumer_sync();
        if (warp < 4 && lane == 0) {
            mbar_arrive(empty_bar + 0);
            mbar_arrive(empty_bar + 8);
        }
        {
            const uint32_t* src = g_qpart + ((hkv * kB + b) * 4 + (tid >> 6)) * 4 * kDh + (tid & 63) * 2;
            uint2 w[4];
            int spins = 0;
            uint32_t bad;
            mbar_wait(full_bar + kQReadAfter * 8, 0);
            do {
                bad = 0;
#pragma unroll
                for (int k = 0; k < 4; k++) w[k] = ld_word2(src + k * kDh);
#pragma unroll
                for (int k = 0; k < 4; k++) bad |= tag_diff(w[k], tag);
            } while (bad && ++spins < kSpinLimit);
            const float q0 = (untag(w[0].x) + untag(w[1].x)) + (untag(w[2].x) + untag(w[3].x));
            const float q1 = (untag(w[0].y) + untag(w[1].y)) + (untag(w[2].y) + untag(w[3].y));
            *reinterpret_cast<uint32_t*>(smem + kOffQ + ((tid >> 6) * kActPitch + (tid & 63) * 2) * 2) = pack_bf16(q0, q1);
        }
        consumer_sync();

        uint32_t qf[8][2];
        const uint32_t q_addr = smem_base + kOffQ + ((g & 3) * kActPitch + 2 * t) * 2;
#pragma unroll
        for (int ks = 0; ks < 8; ks++) {
            const uint32_t v0 = lds32(q_addr + ks * 32), v1 = lds32(q_addr + ks * 32 + 16);
            qf[ks][0] = g < 4 ? v0 : 0u;
            qf[ks][1] = g < 4 ? v1 : 0u;
        }
        const float kScale = 0.08838834764831845f, kLog2e = 1.4426950408889634f;
        float o[8][4];
#pragma unroll
        for (int m = 0; m < 8; m++) o[m][0] = o[m][1] = o[m][2] = o[m][3] = 0.f;
        float m0 = -INFINITY, m1 = -INFINITY, l0 = 0.f, l1 = 0.f;

        constexpr int kWoSlot = (kAttnLoads - 2) % kSlots, kWoPar = ((kAttnLoads - 2) / kSlots) & 1;
        uint32_t* o_dst = pin(g_opart + (((hkv * 4 + 2 * (t & 1)) * kB + b) * 2 + split) * kDh + warp * 16 + g * 2);
        const uint32_t* o_src = pin(g_opart + (head * kB + warp) * 2 * kDh + lane * 4);
        uint32_t* s_dst = pin(g_spart + ((quarter * 32 + warp * 4 + t) * 32 + head) * 32 + g * 4);
        const uint32_t* s_src = pin(g_spart + (quarter * 32 + head) * 1024 + tid * 4);
        __nv_bfloat16* out_dst = pin(out + out_idx);
        const uint32_t wo_addr = pin(proj_addr(ring + kWoSlot * kSlotBytes, warp, lane));
        const uint32_t act_wr = pin(smem_base + kOffAct + warp * kActFragPitch + lane * 8);
        const uint32_t act_rd = pin(smem_base + kOffAct + g * kActFragPitch + t * 8);

        const int r0 = 16 * (warp & 3);
        const uint32_t k_off = (r0 + (lane & 7) + 8 * ((lane >> 3) & 1)) * 128;
        const uint32_t v_off = (r0 + (lane & 7) + 8 * (lane >> 4)) * 128;
        const uint32_t k_sel = lane >> 4, v_sel = (lane >> 3) & 1, sw = lane & 7;
        int slot = 2 + 2 * (warp >> 2), phase = 0;
        float p0, p1, p2, p3;
#pragma unroll 1
        for (int it = 0;; it++) {
            const uint32_t kt = ring + slot * kSlotBytes + k_off;
            const uint32_t vt = ring + (slot + 1) * kSlotBytes + v_off;
            mbar_wait(full_bar + slot * 8, phase);
            float s[4] = {0.f, 0.f, 0.f, 0.f}, s2[4] = {0.f, 0.f, 0.f, 0.f};
#pragma unroll
            for (int ks = 0; ks < 4; ks++) {
                uint32_t a[4], a2[4];
                ldsm_x4(kt + (((2 * ks + k_sel) ^ sw) << 4), a);
                ldsm_x4(kt + 8192 + (((2 * ks + k_sel) ^ sw) << 4), a2);
                mma_bf16(s, a, qf[ks][0], qf[ks][1]);
                mma_bf16(s2, a2, qf[ks + 4][0], qf[ks + 4][1]);
            }
            __syncwarp();
            if (lane == 0) mbar_arrive(empty_bar + slot * 8);
#pragma unroll
            for (int i = 0; i < 4; i += 2) {
                const uint32_t raw = pack_bf16(s[i] + s2[i], s[i + 1] + s2[i + 1]);
                const uint32_t sc = pack_bf16(__uint_as_float(raw << 16) * kScale, __uint_as_float(raw & 0xffff0000u) * kScale);
                s[i] = __uint_as_float(sc << 16) * kLog2e;
                s[i + 1] = __uint_as_float(sc & 0xffff0000u) * kLog2e;
            }
            float x0 = fmaxf(s[0], s[2]), x1 = fmaxf(s[1], s[3]);
#pragma unroll
            for (int off = 4; off < 32; off <<= 1) {
                x0 = fmaxf(x0, __shfl_xor_sync(0xffffffffu, x0, off));
                x1 = fmaxf(x1, __shfl_xor_sync(0xffffffffu, x1, off));
            }
            const float n0 = fmaxf(m0, x0), n1 = fmaxf(m1, x1);
            if (__any_sync(0xffffffffu, n0 > m0 || n1 > m1)) {
                const float a0 = ex2(m0 - n0), a1 = ex2(m1 - n1);
                l0 *= a0;
                l1 *= a1;
#pragma unroll
                for (int m = 0; m < 8; m++) {
                    o[m][0] *= a0; o[m][1] *= a1; o[m][2] *= a0; o[m][3] *= a1;
                }
                m0 = n0;
                m1 = n1;
            }
            p0 = ex2(s[0] - m0), p1 = ex2(s[1] - m1), p2 = ex2(s[2] - m0), p3 = ex2(s[3] - m1);
            l0 += p0 + p2;
            l1 += p1 + p3;
            if (it == kTiles / 2 - 1) break;
            const uint32_t pb0 = movmatrix_t(pack_bf16(p0, p1)), pb1 = movmatrix_t(pack_bf16(p2, p3));
            mbar_wait(full_bar + (slot + 1) * 8, phase);
#pragma unroll
            for (int m = 0; m < 8; m++) {
                uint32_t a[4];
                ldsm_x4_t(vt + (m >> 2) * 8192 + (((2 * (m & 3) + v_sel) ^ sw) << 4), a);
                mma_bf16(o[m], a, pb0, pb1);
            }
            __syncwarp();
            if (lane == 0) mbar_arrive(empty_bar + (slot + 1) * 8);
            slot += 4;
            if (slot >= kSlots) { slot -= kSlots; phase ^= 1; }
            if (it == kTiles / 2 - 2) slot -= warp >> 2;
        }

        {
#pragma unroll
            for (int off = 4; off < 32; off <<= 1) {
                l0 += __shfl_xor_sync(0xffffffffu, l0, off);
                l1 += __shfl_xor_sync(0xffffffffu, l1, off);
            }
            float* stat = reinterpret_cast<float*>(smem + kOffStat);
            if (lane < 2) *reinterpret_cast<float4*>(stat + warp * 8 + lane * 4) = make_float4(m0, l0, m1, l1);
            consumer_sync();
            const float2 ml = *reinterpret_cast<const float2*>(stat + lane * 2);
            float mx = ml.x;
#pragma unroll
            for (int off = 4; off < 32; off <<= 1) mx = fmaxf(mx, __shfl_xor_sync(0xffffffffu, mx, off));
            const float e = ex2(ml.x - mx);
            float lsum = ml.y * e;
#pragma unroll
            for (int off = 4; off < 32; off <<= 1) lsum += __shfl_xor_sync(0xffffffffu, lsum, off);
            const float f = e * rcp_fast(lsum), lse = mx + __log2f(lsum);
            const int hsel = 2 * (t & 1);
            const float f0 = __shfl_sync(0xffffffffu, f, warp * 4 + hsel), f1 = __shfl_sync(0xffffffffu, f, warp * 4 + hsel + 1);
            const int bit = warp * 4 + (g >> 1);
            const uint32_t mark0 = 1u | (((__float_as_uint(__shfl_sync(0xffffffffu, lse, hsel)) >> bit) & 1u) << 1);
            const uint32_t mark1 = 1u | (((__float_as_uint(__shfl_sync(0xffffffffu, lse, hsel + 1)) >> bit) & 1u) << 1);

            float4* os = reinterpret_cast<float4*>(smem + kOffO) + g * 2 + (t & 1);
            if (t < 2) {
#pragma unroll
                for (int m = 0; m < 8; m++)
                    os[(m * 8 + warp) * 16] = make_float4(o[m][0] * f0, o[m][1] * f1, o[m][2] * f0, o[m][3] * f1);
            }
            const uint32_t pf_addr = smem_base + kOffXn + lane * 8;
            sts64(pf_addr + warp * 256, movmatrix_t(pack_bf16(p0 * f0, p1 * f1)), movmatrix_t(pack_bf16(p2 * f0, p3 * f1)));
            consumer_sync();
            float c[4][4];
#pragma unroll
            for (int j = 0; j < 4; j++) {
                const float4 u = os[(warp * 8 + j) * 16], v = os[(warp * 8 + j + 4) * 16];
                c[j][0] = u.x + v.x, c[j][1] = u.y + v.y, c[j][2] = u.z + v.z, c[j][3] = u.w + v.w;
            }
            uint2 pf[8];
#pragma unroll
            for (int j = 0; j < 8; j++) pf[j] = lds64(pf_addr + j * 256);
            constexpr int kLastV = (kAttnLoads - 4) % kSlots, kLastPar = ((kAttnLoads - 4) / kSlots) & 1;
            const uint32_t va = proj_addr(ring + kLastV * kSlotBytes, warp, lane);
#pragma unroll
            for (int u = 0; u < 2; u++) {
                mbar_wait(full_bar + (kLastV + u) * 8, kLastPar);
#pragma unroll
                for (int j = 0; j < 4; j++) {
                    uint32_t a[4];
                    ldsm_x4_t(va + u * kSlotBytes + j * 2048, a);
                    mma_bf16(c[j], a, pf[u * 4 + j].x, pf[u * 4 + j].y);
                }
            }
            if (t < 2) {
                float r[4];
#pragma unroll
                for (int i = 0; i < 4; i++) r[i] = (c[0][i] + c[1][i]) + (c[2][i] + c[3][i]);
                st_word2(o_dst, (__float_as_uint(r[0]) & ~kTagMask) | mark0, mail_word(r[2]));
                st_word2(o_dst + kB * 2 * kDh, (__float_as_uint(r[1]) & ~kTagMask) | mark1, mail_word(r[3]));
            }
        }

        mbar_wait(gate_bar, 0);

        const uint32_t act_bar = gate_bar + 8;
        {
            uint4 w0, w1;
            int spins = 0;
            do {
                w0 = ld_word4(o_src), w1 = ld_word4(o_src + kDh);
            } while (!__all_sync(0xffffffffu, mail_full(w0, w1)) && ++spins < kSpinLimit);
            const float ls0 = __uint_as_float(__ballot_sync(0xffffffffu, w0.x & 2u));
            const float ls1 = __uint_as_float(__ballot_sync(0xffffffffu, w1.x & 2u));
            const float c0 = rcp_fast(1.0f + ex2(ls1 - ls0));
            const float c1 = rcp_fast(1.0f + ex2(ls0 - ls1));
            sts64(act_wr, pack_bf16(untag(w0.x) * c0 + untag(w1.x) * c1, untag(w0.z) * c0 + untag(w1.z) * c1),
                  pack_bf16(untag(w0.y) * c0 + untag(w1.y) * c1, untag(w0.w) * c0 + untag(w1.w) * c1));
            __syncwarp();
            if (lane == 0) mbar_arrive(act_bar);
        }

        {
            uint32_t a[8][4];
#pragma unroll
            for (int u = 0; u < 2; u++) {
                mbar_wait(full_bar + (kWoSlot + u) * 8, kWoPar);
#pragma unroll
                for (int j = 0; j < 4; j++) ldsm_x4_t(wo_addr + u * kSlotBytes + j * 2048, a[u * 4 + j]);
            }
            mbar_wait(act_bar, 0);
            float c[4][4];
#pragma unroll
            for (int j = 0; j < 4; j++) c[j][0] = c[j][1] = c[j][2] = c[j][3] = 0.f;
#pragma unroll
            for (int ks = 0; ks < 8; ks++) {
                const uint2 bf = lds64(act_rd + ks * 32);
                mma_bf16(c[ks & 3], a[ks], bf.x, bf.y);
            }
            st_word4(s_dst, mail_word((c[0][0] + c[1][0]) + (c[2][0] + c[3][0])), mail_word((c[0][1] + c[1][1]) + (c[2][1] + c[3][1])),
                     mail_word((c[0][2] + c[1][2]) + (c[2][2] + c[3][2])), mail_word((c[0][3] + c[1][3]) + (c[2][3] + c[3][3])));
        }

        {
            uint4 w;
            int spins = 0;
            do {
                w = ld_word4(s_src);
            } while (!__all_sync(0xffffffffu, mail_full(w)) && ++spins < kSpinLimit);
            float4 v = make_float4(untag(w.x), untag(w.y), untag(w.z), untag(w.w));
#pragma unroll
            for (int off = 8; off < 32; off <<= 1) {
                v.x += __shfl_xor_sync(0xffffffffu, v.x, off);
                v.y += __shfl_xor_sync(0xffffffffu, v.y, off);
                v.z += __shfl_xor_sync(0xffffffffu, v.z, off);
                v.w += __shfl_xor_sync(0xffffffffu, v.w, off);
            }
            if (lane < 8) *reinterpret_cast<float4*>(red + warp * 32 + lane * 4) = v;
            asm volatile("bar.sync 2, 288;" ::: "memory");
            if (warp == 0) {
                float p[kConsumerWarps];
#pragma unroll
                for (int k = 0; k < kConsumerWarps; k++) p[k] = red[k * 32 + lane];
                const float s = ((p[0] + p[1]) + (p[2] + p[3])) + ((p[4] + p[5]) + (p[6] + p[7]));
                const __nv_bfloat16 r = __float2bfloat16_rn(red[288 + lane] + round_bf16(round_bf16(s) * red[256 + lane]));
                asm volatile("st.global.b16 [%0], %1;" ::"l"(out_dst), "h"(__bfloat16_as_ushort(r)) : "memory");
            }
        }
        return;
    }

    {
        const int krow = (lane & 7) + 8 * (lane >> 4);
        const int csel = (lane >> 3) & 1;
        const uint32_t a_base = ring + warp * 2048 + krow * 128;
        float acc[2][4][4];
#pragma unroll
        for (int m = 0; m < 4; m++)
#pragma unroll
            for (int i = 0; i < 4; i++) acc[0][m][i] = acc[1][m][i] = 0.f;
        int slot = 0, phase = 0;
        auto step = [&](float (&c)[4][4], uint32_t b0, uint32_t b1) {
            mbar_wait(full_bar + slot * 8, phase);
#pragma unroll
            for (int m = 0; m < 4; m++) {
                uint32_t a[4];
                ldsm_x4_t(a_base + slot * kSlotBytes + (((2 * m + csel) ^ (lane & 7)) << 4), a);
                mma_bf16(c[m], a, b0, b1);
            }
            __syncwarp();
            if (lane == 0) mbar_arrive(empty_bar + slot * 8);
            if (++slot == kSlots) { slot = 0; phase ^= 1; }
        };
        const uint32_t xn_addr = smem_base + kOffXn + (g * kXnPitch + 2 * t) * 2;
#pragma unroll 1
        for (int ks = 0; ks < kGluSteps1; ks++) {
            const uint32_t b0 = lds32(xn_addr + ks * 32), b1 = lds32(xn_addr + ks * 32 + 16);
            step(acc[0], b0, b1);
            step(acc[1], b0, b1);
        }
        __nv_bfloat16* hs = reinterpret_cast<__nv_bfloat16*>(smem + kOffO);
#pragma unroll
        for (int m = 0; m < 4; m++)
#pragma unroll
            for (int i = 0; i < 4; i++) {
                const float hv = round_bf16(sigmoid_fast(round_bf16(acc[0][m][i]))) * round_bf16(acc[1][m][i]);
                if (warp < kGluChunks)
                    hs[(2 * t + (i & 1)) * kHPitch + warp * 64 + m * 16 + g + 8 * (i >> 1)] = __float2bfloat16_rn(hv);
                acc[0][m][i] = 0.f;
            }
        consumer_sync();
        const uint32_t h_addr = smem_base + kOffO + (g * kHPitch + 2 * t) * 2;
#pragma unroll 1
        for (int ks = 0; ks < kGluSteps2; ks++) step(acc[0], lds32(h_addr + ks * 32), lds32(h_addr + ks * 32 + 16));
        uint32_t* dst = g_gpart + (quarter * kB + 2 * t) * kD + warp * 64 + g;
#pragma unroll
        for (int m = 0; m < 4; m++)
#pragma unroll
            for (int i = 0; i < 4; i++) st_word(dst + (i & 1) * kD + m * 16 + 8 * (i >> 1), tag_word(acc[0][m][i], tag));
    }
}

typedef CUresult (*EncodeTiledFn)(CUtensorMap*, CUtensorMapDataType, cuuint32_t, void*, const cuuint64_t*, const cuuint64_t*,
                                  const cuuint32_t*, const cuuint32_t*, CUtensorMapInterleave, CUtensorMapSwizzle,
                                  CUtensorMapL2promotion, CUtensorMapFloatOOBfill);

void encode_map(EncodeTiledFn fn, CUtensorMap* map, void* ptr, uint64_t rows, uint64_t cols, uint32_t box_rows, uint32_t box_chunks) {
    const cuuint64_t dims[3] = {64, rows, cols / 64};
    const cuuint64_t strides[2] = {cols * 2, 128};
    const cuuint32_t box[3] = {64, box_rows, box_chunks};
    const cuuint32_t elem[3] = {1, 1, 1};
    fn(map, CU_TENSOR_MAP_DATA_TYPE_BFLOAT16, 3, ptr, dims, strides, box, elem, CU_TENSOR_MAP_INTERLEAVE_NONE,
       CU_TENSOR_MAP_SWIZZLE_128B, CU_TENSOR_MAP_L2_PROMOTION_NONE, CU_TENSOR_MAP_FLOAT_OOB_FILL_NONE);
}

}

extern "C" void kernel_launch(void* const* d_in, const int* in_sizes, int n_in, void* d_out, int out_size) {
    (void)in_sizes; (void)n_in; (void)out_size;
    void* fn_ptr = nullptr;
    cudaDriverEntryPointQueryResult qr;
    cudaGetDriverEntryPoint("cuTensorMapEncodeTiled", &fn_ptr, cudaEnableDefault, &qr);
    EncodeTiledFn fn = (EncodeTiledFn)fn_ptr;

    Maps maps;
    encode_map(fn, &maps.k, d_in[1], (uint64_t)kB * kHkv * kSk, kDh, kTileKeys, 2);
    encode_map(fn, &maps.v, d_in[2], (uint64_t)kB * kHkv * kSk, kDh, kTileKeys, 2);
    encode_map(fn, &maps.wq, d_in[3], kD, 4096, 64, 2);
    encode_map(fn, &maps.wo, d_in[4], 4096, kD, 64, 2);
    encode_map(fn, &maps.wg, d_in[6], kD, kF, 16, kGluChunks);
    encode_map(fn, &maps.wu, d_in[7], kD, kF, 16, kGluChunks);
    encode_map(fn, &maps.wd, d_in[8], kF, kD, 16, 8);

    cudaFuncSetAttribute(fused_decode_kernel, cudaFuncAttributeMaxDynamicSharedMemorySize, kSmemBytes);
    fused_decode_kernel<<<kGrid, kThreads, kSmemBytes, cudaStreamPerThread>>>(
        (const __nv_bfloat16*)d_in[0], (__nv_bfloat16*)d_out, (const char*)d_in[3], maps);
}
```
